```python
import torch

def _softmax(x, axis=-1):
    return torch.softmax(x, dim=axis)

def _gelu(x):
    return torch.nn.functional.gelu(x, approximate='tanh')

def _silu(x):
    return torch.nn.functional.silu(x)

def _sigmoid(x):
    return torch.sigmoid(x)

def _layernorm(x, axis=-1, eps=1e-05):
    m = x.mean(dim=axis, keepdim=True)
    v = x.var(dim=axis, keepdim=True, unbiased=False)
    return (x - m) / torch.sqrt(v + eps)

def _scatter_add(tgt, idx, src, axis=0):
    return tgt.clone().index_add_(axis, idx, src)

def _segment_sum(src, seg, n):
    out = torch.zeros((n,) + src.shape[1:], dtype=src.dtype)
    return out.index_add_(0, seg, src)

def _pad(x, pw):
    flat = tuple((v for pair in reversed(pw) for v in pair))
    return torch.nn.functional.pad(x, flat)
kernel_name = 'standalone__conformer_family_zipformer__speech'

def setup_inputs():

    _w = lambda a: (lambda t: t.to(torch.bfloat16) if t.is_floating_point() else t)(torch.as_tensor(a))
    B, T, D, K, H = (2, 4000, 256, 5, 4)
    sc = 0.1
    return {'x': _w((lambda *s: torch.randn(*s, dtype=torch.bfloat16) * 0.8)(B, T, D)), 'w_ff1a': _w((lambda *s: torch.randn(*s, dtype=torch.bfloat16) * 0.8)(D, 4 * D) * sc), 'w_ff1b': _w((lambda *s: torch.randn(*s, dtype=torch.bfloat16) * 0.8)(4 * D, D) * sc), 'w_qkv': _w((lambda *s: torch.randn(*s, dtype=torch.bfloat16) * 0.8)(D, 3 * D) * sc), 'w_o': _w((lambda *s: torch.randn(*s, dtype=torch.bfloat16) * 1.6)(D, D) * sc), 'w_pw1': _w((lambda *s: torch.randn(*s, dtype=torch.bfloat16) * 1.6)(D, 2 * D) * sc), 'dw': _w((lambda *s: torch.randn(*s, dtype=torch.bfloat16) * 0.4)(K, D)), 'w_pw2': _w((lambda *s: torch.randn(*s, dtype=torch.bfloat16) * 0.4)(D, D) * sc), 'w_ff2a': _w((lambda *s: torch.randn(*s, dtype=torch.bfloat16) * 0.8)(D, 4 * D) * sc), 'w_ff2b': _w((lambda *s: torch.randn(*s, dtype=torch.bfloat16) * 0.8)(4 * D, D) * sc)}

def reference(x, w_ff1a, w_ff1b, w_qkv, w_o, w_pw1, dw, w_pw2, w_ff2a, w_ff2b):
    B, T, D = x.shape
    K = dw.shape[0]
    H = 4
    Dh = D // H
    h = _layernorm(x, axis=-1)
    h = _silu(h @ w_ff1a) @ w_ff1b
    x = x + 0.5 * h
    h = _layernorm(x, axis=-1)
    qkv = h @ w_qkv
    q = (lambda x, *d: x.permute(*d))(qkv[..., :D].reshape(B, T, H, Dh), 0, 2, 1, 3)
    k = (lambda x, *d: x.permute(*d))(qkv[..., D:2 * D].reshape(B, T, H, Dh), 0, 2, 1, 3)
    v = (lambda x, *d: x.permute(*d))(qkv[..., 2 * D:].reshape(B, T, H, Dh), 0, 2, 1, 3)
    scale = Dh ** (-0.5)
    scores = torch.einsum('bhqd,bhkd->bhqk', q, k) * scale
    p = _softmax(scores, axis=-1)
    att = torch.einsum('bhqk,bhkd->bhqd', p, v)
    att = (lambda x, *d: x.permute(*d))(att, 0, 2, 1, 3).reshape(B, T, D)
    x = x + att @ w_o
    h = _layernorm(x, axis=-1)
    h = h @ w_pw1
    a, b = (h[..., :D].clone(), h[..., D:].clone())
    h = a * _sigmoid(b)
    pad = K // 2
    hp = _pad(h, ((0, 0), (pad, pad), (0, 0)))
    c = torch.zeros_like(h)
    for i in range(K):
        c = c + hp[:, i:i + T, :] * dw[i][None, None, :]
    x = x + _silu(c) @ w_pw2
    h = _layernorm(x, axis=-1)
    h = _silu(h @ w_ff2a) @ w_ff2b
    x = x + 0.5 * h
    return _layernorm(x, axis=-1)
```

```cpp
#include <cuda_runtime.h>
#include <cuda.h>
#include <cuda_bf16.h>
#include <stdint.h>
#include <type_traits>

constexpr int T_LEN = 4000;
constexpr int M_TOT = 8000;
constexpr float LN_EPS = 1e-5f;
constexpr float Q_SCALE = 0.125f * 1.4426950408889634f;

__device__ __align__(1024) __nv_bfloat16 g_x2[M_TOT * 256];
__device__ __align__(1024) __nv_bfloat16 g_qkv[M_TOT * 768];
__device__ __align__(1024) __nv_bfloat16 g_att[M_TOT * 256];

#include <stdio.h>
#include <stdlib.h>
constexpr int USE_PDL = 1;

template<int TB> __device__ __forceinline__ void wgmma_rs_n64(float (&d)[32], uint32_t a0, uint32_t a1, uint32_t a2, uint32_t a3, uint64_t db, int sd) {
  asm volatile("{\n.reg .pred p;\nsetp.ne.b32 p, %37, 0;\n"
    "wgmma.mma_async.sync.aligned.m64n64k16.f32.bf16.bf16 "
    "{%0, %1, %2, %3, %4, %5, %6, %7, %8, %9, %10, %11, %12, %13, %14, %15, "
    "%16, %17, %18, %19, %20, %21, %22, %23, %24, %25, %26, %27, %28, %29, %30, %31}, "
    "{%32, %33, %34, %35}, %36, p, 1, 1, %38;\n}\n"
    : "+f"(d[0]), "+f"(d[1]), "+f"(d[2]), "+f"(d[3]), "+f"(d[4]), "+f"(d[5]), "+f"(d[6]), "+f"(d[7]), "+f"(d[8]), "+f"(d[9]), "+f"(d[10]), "+f"(d[11]), "+f"(d[12]), "+f"(d[13]), "+f"(d[14]), "+f"(d[15]), "+f"(d[16]), "+f"(d[17]), "+f"(d[18]), "+f"(d[19]), "+f"(d[20]), "+f"(d[21]), "+f"(d[22]), "+f"(d[23]), "+f"(d[24]), "+f"(d[25]), "+f"(d[26]), "+f"(d[27]), "+f"(d[28]), "+f"(d[29]), "+f"(d[30]), "+f"(d[31])
    : "r"(a0), "r"(a1), "r"(a2), "r"(a3), "l"(db), "r"(sd), "n"(TB));
}
template<int TB> __device__ __forceinline__ void wgmma_rs_n72(float (&d)[36], uint32_t a0, uint32_t a1, uint32_t a2, uint32_t a3, uint64_t db, int sd) {
  asm volatile("{\n.reg .pred p;\nsetp.ne.b32 p, %41, 0;\n"
    "wgmma.mma_async.sync.aligned.m64n72k16.f32.bf16.bf16 "
    "{%0, %1, %2, %3, %4, %5, %6, %7, %8, %9, %10, %11, %12, %13, %14, %15, "
    "%16, %17, %18, %19, %20, %21, %22, %23, %24, %25, %26, %27, %28, %29, %30, %31, "
    "%32, %33, %34, %35}, "
    "{%36, %37, %38, %39}, %40, p, 1, 1, %42;\n}\n"
    : "+f"(d[0]), "+f"(d[1]), "+f"(d[2]), "+f"(d[3]), "+f"(d[4]), "+f"(d[5]), "+f"(d[6]), "+f"(d[7]), "+f"(d[8]), "+f"(d[9]), "+f"(d[10]), "+f"(d[11]), "+f"(d[12]), "+f"(d[13]), "+f"(d[14]), "+f"(d[15]), "+f"(d[16]), "+f"(d[17]), "+f"(d[18]), "+f"(d[19]), "+f"(d[20]), "+f"(d[21]), "+f"(d[22]), "+f"(d[23]), "+f"(d[24]), "+f"(d[25]), "+f"(d[26]), "+f"(d[27]), "+f"(d[28]), "+f"(d[29]), "+f"(d[30]), "+f"(d[31]), "+f"(d[32]), "+f"(d[33]), "+f"(d[34]), "+f"(d[35])
    : "r"(a0), "r"(a1), "r"(a2), "r"(a3), "l"(db), "r"(sd), "n"(TB));
}
template<int TB> __device__ __forceinline__ void wgmma_rs_n128(float (&d)[64], uint32_t a0, uint32_t a1, uint32_t a2, uint32_t a3, uint64_t db, int sd) {
  asm volatile("{\n.reg .pred p;\nsetp.ne.b32 p, %69, 0;\n"
    "wgmma.mma_async.sync.aligned.m64n128k16.f32.bf16.bf16 "
    "{%0, %1, %2, %3, %4, %5, %6, %7, %8, %9, %10, %11, %12, %13, %14, %15, "
    "%16, %17, %18, %19, %20, %21, %22, %23, %24, %25, %26, %27, %28, %29, %30, %31, "
    "%32, %33, %34, %35, %36, %37, %38, %39, %40, %41, %42, %43, %44, %45, %46, %47, "
    "%48, %49, %50, %51, %52, %53, %54, %55, %56, %57, %58, %59, %60, %61, %62, %63}, "
    "{%64, %65, %66, %67}, %68, p, 1, 1, %70;\n}\n"
    : "+f"(d[0]), "+f"(d[1]), "+f"(d[2]), "+f"(d[3]), "+f"(d[4]), "+f"(d[5]), "+f"(d[6]), "+f"(d[7]), "+f"(d[8]), "+f"(d[9]), "+f"(d[10]), "+f"(d[11]), "+f"(d[12]), "+f"(d[13]), "+f"(d[14]), "+f"(d[15]), "+f"(d[16]), "+f"(d[17]), "+f"(d[18]), "+f"(d[19]), "+f"(d[20]), "+f"(d[21]), "+f"(d[22]), "+f"(d[23]), "+f"(d[24]), "+f"(d[25]), "+f"(d[26]), "+f"(d[27]), "+f"(d[28]), "+f"(d[29]), "+f"(d[30]), "+f"(d[31]), "+f"(d[32]), "+f"(d[33]), "+f"(d[34]), "+f"(d[35]), "+f"(d[36]), "+f"(d[37]), "+f"(d[38]), "+f"(d[39]), "+f"(d[40]), "+f"(d[41]), "+f"(d[42]), "+f"(d[43]), "+f"(d[44]), "+f"(d[45]), "+f"(d[46]), "+f"(d[47]), "+f"(d[48]), "+f"(d[49]), "+f"(d[50]), "+f"(d[51]), "+f"(d[52]), "+f"(d[53]), "+f"(d[54]), "+f"(d[55]), "+f"(d[56]), "+f"(d[57]), "+f"(d[58]), "+f"(d[59]), "+f"(d[60]), "+f"(d[61]), "+f"(d[62]), "+f"(d[63])
    : "r"(a0), "r"(a1), "r"(a2), "r"(a3), "l"(db), "r"(sd), "n"(TB));
}
template<int TB> __device__ __forceinline__ void wgmma_ss_n128(float (&d)[64], uint64_t da, uint64_t db, int sd) {
  asm volatile("{\n.reg .pred p;\nsetp.ne.b32 p, %66, 0;\n"
    "wgmma.mma_async.sync.aligned.m64n128k16.f32.bf16.bf16 "
    "{%0, %1, %2, %3, %4, %5, %6, %7, %8, %9, %10, %11, %12, %13, %14, %15, "
    "%16, %17, %18, %19, %20, %21, %22, %23, %24, %25, %26, %27, %28, %29, %30, %31, "
    "%32, %33, %34, %35, %36, %37, %38, %39, %40, %41, %42, %43, %44, %45, %46, %47, "
    "%48, %49, %50, %51, %52, %53, %54, %55, %56, %57, %58, %59, %60, %61, %62, %63}, "
    "%64, %65, p, 1, 1, 0, %67;\n}\n"
    : "+f"(d[0]), "+f"(d[1]), "+f"(d[2]), "+f"(d[3]), "+f"(d[4]), "+f"(d[5]), "+f"(d[6]), "+f"(d[7]), "+f"(d[8]), "+f"(d[9]), "+f"(d[10]), "+f"(d[11]), "+f"(d[12]), "+f"(d[13]), "+f"(d[14]), "+f"(d[15]), "+f"(d[16]), "+f"(d[17]), "+f"(d[18]), "+f"(d[19]), "+f"(d[20]), "+f"(d[21]), "+f"(d[22]), "+f"(d[23]), "+f"(d[24]), "+f"(d[25]), "+f"(d[26]), "+f"(d[27]), "+f"(d[28]), "+f"(d[29]), "+f"(d[30]), "+f"(d[31]), "+f"(d[32]), "+f"(d[33]), "+f"(d[34]), "+f"(d[35]), "+f"(d[36]), "+f"(d[37]), "+f"(d[38]), "+f"(d[39]), "+f"(d[40]), "+f"(d[41]), "+f"(d[42]), "+f"(d[43]), "+f"(d[44]), "+f"(d[45]), "+f"(d[46]), "+f"(d[47]), "+f"(d[48]), "+f"(d[49]), "+f"(d[50]), "+f"(d[51]), "+f"(d[52]), "+f"(d[53]), "+f"(d[54]), "+f"(d[55]), "+f"(d[56]), "+f"(d[57]), "+f"(d[58]), "+f"(d[59]), "+f"(d[60]), "+f"(d[61]), "+f"(d[62]), "+f"(d[63])
    : "l"(da), "l"(db), "r"(sd), "n"(TB));
}
template<int TB> __device__ __forceinline__ void wgmma_ss_n256(float (&d)[128], uint64_t da, uint64_t db, int sd) {
  asm volatile("{\n.reg .pred p;\nsetp.ne.b32 p, %130, 0;\n"
    "wgmma.mma_async.sync.aligned.m64n256k16.f32.bf16.bf16 "
    "{%0, %1, %2, %3, %4, %5, %6, %7, %8, %9, %10, %11, %12, %13, %14, %15, "
    "%16, %17, %18, %19, %20, %21, %22, %23, %24, %25, %26, %27, %28, %29, %30, %31, "
    "%32, %33, %34, %35, %36, %37, %38, %39, %40, %41, %42, %43, %44, %45, %46, %47, "
    "%48, %49, %50, %51, %52, %53, %54, %55, %56, %57, %58, %59, %60, %61, %62, %63, "
    "%64, %65, %66, %67, %68, %69, %70, %71, %72, %73, %74, %75, %76, %77, %78, %79, "
    "%80, %81, %82, %83, %84, %85, %86, %87, %88, %89, %90, %91, %92, %93, %94, %95, "
    "%96, %97, %98, %99, %100, %101, %102, %103, %104, %105, %106, %107, %108, %109, %110, %111, "
    "%112, %113, %114, %115, %116, %117, %118, %119, %120, %121, %122, %123, %124, %125, %126, %127}, "
    "%128, %129, p, 1, 1, 0, %131;\n}\n"
    : "+f"(d[0]), "+f"(d[1]), "+f"(d[2]), "+f"(d[3]), "+f"(d[4]), "+f"(d[5]), "+f"(d[6]), "+f"(d[7]), "+f"(d[8]), "+f"(d[9]), "+f"(d[10]), "+f"(d[11]), "+f"(d[12]), "+f"(d[13]), "+f"(d[14]), "+f"(d[15]), "+f"(d[16]), "+f"(d[17]), "+f"(d[18]), "+f"(d[19]), "+f"(d[20]), "+f"(d[21]), "+f"(d[22]), "+f"(d[23]), "+f"(d[24]), "+f"(d[25]), "+f"(d[26]), "+f"(d[27]), "+f"(d[28]), "+f"(d[29]), "+f"(d[30]), "+f"(d[31]), "+f"(d[32]), "+f"(d[33]), "+f"(d[34]), "+f"(d[35]), "+f"(d[36]), "+f"(d[37]), "+f"(d[38]), "+f"(d[39]), "+f"(d[40]), "+f"(d[41]), "+f"(d[42]), "+f"(d[43]), "+f"(d[44]), "+f"(d[45]), "+f"(d[46]), "+f"(d[47]), "+f"(d[48]), "+f"(d[49]), "+f"(d[50]), "+f"(d[51]), "+f"(d[52]), "+f"(d[53]), "+f"(d[54]), "+f"(d[55]), "+f"(d[56]), "+f"(d[57]), "+f"(d[58]), "+f"(d[59]), "+f"(d[60]), "+f"(d[61]), "+f"(d[62]), "+f"(d[63]), "+f"(d[64]), "+f"(d[65]), "+f"(d[66]), "+f"(d[67]), "+f"(d[68]), "+f"(d[69]), "+f"(d[70]), "+f"(d[71]), "+f"(d[72]), "+f"(d[73]), "+f"(d[74]), "+f"(d[75]), "+f"(d[76]), "+f"(d[77]), "+f"(d[78]), "+f"(d[79]), "+f"(d[80]), "+f"(d[81]), "+f"(d[82]), "+f"(d[83]), "+f"(d[84]), "+f"(d[85]), "+f"(d[86]), "+f"(d[87]), "+f"(d[88]), "+f"(d[89]), "+f"(d[90]), "+f"(d[91]), "+f"(d[92]), "+f"(d[93]), "+f"(d[94]), "+f"(d[95]), "+f"(d[96]), "+f"(d[97]), "+f"(d[98]), "+f"(d[99]), "+f"(d[100]), "+f"(d[101]), "+f"(d[102]), "+f"(d[103]), "+f"(d[104]), "+f"(d[105]), "+f"(d[106]), "+f"(d[107]), "+f"(d[108]), "+f"(d[109]), "+f"(d[110]), "+f"(d[111]), "+f"(d[112]), "+f"(d[113]), "+f"(d[114]), "+f"(d[115]), "+f"(d[116]), "+f"(d[117]), "+f"(d[118]), "+f"(d[119]), "+f"(d[120]), "+f"(d[121]), "+f"(d[122]), "+f"(d[123]), "+f"(d[124]), "+f"(d[125]), "+f"(d[126]), "+f"(d[127])
    : "l"(da), "l"(db), "r"(sd), "n"(TB));
}

__device__ __forceinline__ uint32_t smem_u32(const void* p) { return (uint32_t)__cvta_generic_to_shared(p); }
__device__ __forceinline__ void wg_fence() { asm volatile("wgmma.fence.sync.aligned;" ::: "memory"); }
__device__ __forceinline__ void wg_commit() { asm volatile("wgmma.commit_group.sync.aligned;" ::: "memory"); }
template <int N> __device__ __forceinline__ void wg_wait() { asm volatile("wgmma.wait_group.sync.aligned %0;" ::"n"(N) : "memory"); }
__device__ __forceinline__ void mbar_init(uint32_t bar, int cnt) { asm volatile("mbarrier.init.shared::cta.b64 [%0], %1;" ::"r"(bar), "r"(cnt) : "memory"); }
__device__ __forceinline__ void mbar_inval(uint32_t bar) { asm volatile("mbarrier.inval.shared::cta.b64 [%0];" ::"r"(bar) : "memory"); }
__device__ __forceinline__ void mbar_expect_tx(uint32_t bar, int bytes) { asm volatile("mbarrier.arrive.expect_tx.shared::cta.b64 _, [%0], %1;" ::"r"(bar), "r"(bytes) : "memory"); }
__device__ __forceinline__ void mbar_arrive(uint32_t bar) { asm volatile("mbarrier.arrive.shared::cta.b64 _, [%0];" ::"r"(bar) : "memory"); }
__device__ __forceinline__ bool mbar_try(uint32_t bar, uint32_t parity) {
  uint32_t ok;
  asm volatile("{\n.reg .pred p;\nmbarrier.try_wait.parity.shared::cta.b64 p, [%1], %2;\nselp.u32 %0, 1, 0, p;\n}" : "=r"(ok) : "r"(bar), "r"(parity) : "memory");
  return ok != 0;
}
__device__ __forceinline__ void mbar_wait(uint32_t bar, uint32_t parity) {
  if (mbar_try(bar, parity)) return;
  uint32_t n = 0;
  while (!mbar_try(bar, parity)) { if (++n > (1u << 22)) __trap(); }
}
__device__ __forceinline__ void mbar_wait_wd(uint32_t bar, uint32_t parity) { while (!mbar_try(bar, parity)) {} }
__device__ __forceinline__ void fence_barrier_init() { asm volatile("fence.mbarrier_init.release.cluster;" ::: "memory"); }
__device__ __forceinline__ void fence_async_smem() { asm volatile("fence.proxy.async.shared::cta;" ::: "memory"); }
__device__ __forceinline__ void tma_load_2d(uint32_t dst, const CUtensorMap* tm, uint32_t bar, int c0, int c1) {
  asm volatile("cp.async.bulk.tensor.2d.shared::cluster.global.mbarrier::complete_tx::bytes [%0], [%1, {%3, %4}], [%2];"
               ::"r"(dst), "l"(tm), "r"(bar), "r"(c0), "r"(c1) : "memory");
}
__device__ __forceinline__ void tma_load_3d(uint32_t dst, const CUtensorMap* tm, uint32_t bar, int c0, int c1, int c2) {
  asm volatile("cp.async.bulk.tensor.3d.shared::cluster.global.mbarrier::complete_tx::bytes [%0], [%1, {%3, %4, %5}], [%2];"
               ::"r"(dst), "l"(tm), "r"(bar), "r"(c0), "r"(c1), "r"(c2) : "memory");
}
__device__ __forceinline__ void tma_load_4d(uint32_t dst, const CUtensorMap* tm, uint32_t bar, int c0, int c1, int c2, int c3) {
  asm volatile("cp.async.bulk.tensor.4d.shared::cluster.global.mbarrier::complete_tx::bytes [%0], [%1, {%3, %4, %5, %6}], [%2];"
               ::"r"(dst), "l"(tm), "r"(bar), "r"(c0), "r"(c1), "r"(c2), "r"(c3) : "memory");
}
__device__ __forceinline__ void tma_store_3d(const CUtensorMap* tm, uint32_t src, int c0, int c1, int c2) {
  asm volatile("cp.async.bulk.tensor.3d.global.shared::cta.bulk_group [%0, {%2, %3, %4}], [%1];" ::"l"(tm), "r"(src), "r"(c0), "r"(c1), "r"(c2) : "memory");
}
__device__ __forceinline__ void bulk_commit() { asm volatile("cp.async.bulk.commit_group;" ::: "memory"); }
template <int N> __device__ __forceinline__ void bulk_wait_read() { asm volatile("cp.async.bulk.wait_group.read %0;" ::"n"(N) : "memory"); }
template <int N> __device__ __forceinline__ void bulk_wait() { asm volatile("cp.async.bulk.wait_group %0;" ::"n"(N) : "memory"); }
__device__ __forceinline__ void prefetch_tmap(const CUtensorMap* tm) { asm volatile("prefetch.tensormap [%0];" ::"l"(tm) : "memory"); }
__device__ __forceinline__ void pdl_wait() { asm volatile("griddepcontrol.wait;" ::: "memory"); }
__device__ __forceinline__ void pdl_launch() { asm volatile("griddepcontrol.launch_dependents;" ::: "memory"); }
__device__ __forceinline__ void nbar_sync(int id, int n) { asm volatile("bar.sync %0, %1;" ::"r"(id), "r"(n) : "memory"); }
__device__ __forceinline__ void nbar_arrive(int id, int n) { asm volatile("bar.arrive %0, %1;" ::"r"(id), "r"(n) : "memory"); }
__device__ __forceinline__ void nbar_arrive_if(int id, int n, bool on) {
  asm volatile("{\n.reg .pred p;\nsetp.ne.u32 p, %2, 0;\n@p bar.arrive %0, %1;\n}" ::"r"(id), "r"(n), "r"((uint32_t)on) : "memory");
}
__device__ __forceinline__ bool nbar_or(int id, int n, bool v) {
  uint32_t r;
  asm volatile("{\n.reg .pred p, q;\nsetp.ne.u32 q, %3, 0;\nbar.red.or.pred p, %1, %2, q;\nselp.u32 %0, 1, 0, p;\n}" : "=r"(r) : "r"(id), "r"(n), "r"((uint32_t)v) : "memory");
  return r != 0;
}
__device__ __forceinline__ bool elect_one() {
  uint32_t p; asm volatile("{\n.reg .pred p;\nelect.sync _|p, 0xffffffff;\nselp.u32 %0, 1, 0, p;\n}" : "=r"(p)); return p != 0;
}
template <int N> __device__ __forceinline__ void reg_alloc() { asm volatile("setmaxnreg.inc.sync.aligned.u32 %0;" ::"n"(N)); }
template <int N> __device__ __forceinline__ void reg_dealloc() { asm volatile("setmaxnreg.dec.sync.aligned.u32 %0;" ::"n"(N)); }
__device__ __forceinline__ float ex2f(float x) { float y; asm("ex2.approx.ftz.f32 %0, %1;" : "=f"(y) : "f"(x)); return y; }
__device__ __forceinline__ float rsqrt_f(float x) { float y; asm("rsqrt.approx.ftz.f32 %0, %1;" : "=f"(y) : "f"(x)); return y; }
__device__ __forceinline__ float rcp_f(float x) { float y; asm("rcp.approx.ftz.f32 %0, %1;" : "=f"(y) : "f"(x)); return y; }
__device__ __forceinline__ float tanh_f(float x) { float y; asm("tanh.approx.f32 %0, %1;" : "=f"(y) : "f"(x)); return y; }
__device__ __forceinline__ uint32_t pack_bf16(float lo, float hi) {
  uint32_t r; asm("cvt.rn.bf16x2.f32 %0, %1, %2;" : "=r"(r) : "f"(hi), "f"(lo)); return r;
}
__device__ __forceinline__ float bf_lo(uint32_t v) { return __uint_as_float(v << 16); }
__device__ __forceinline__ float bf_hi(uint32_t v) { return __uint_as_float(v & 0xffff0000u); }
__device__ __forceinline__ uint32_t hfma2_bf16(uint32_t a, uint32_t b, uint32_t c) {
  uint32_t r; asm("fma.rn.bf16x2 %0, %1, %2, %3;" : "=r"(r) : "r"(a), "r"(b), "r"(c)); return r;
}
__device__ __forceinline__ uint32_t hmul2_bf16(uint32_t a, uint32_t b) {
  uint32_t r; asm("mul.rn.bf16x2 %0, %1, %2;" : "=r"(r) : "r"(a), "r"(b)); return r;
}
template <int OFF> __device__ __forceinline__ void stsm4(uint32_t addr, uint32_t r0, uint32_t r1, uint32_t r2, uint32_t r3) {
  asm volatile("stmatrix.sync.aligned.m8n8.x4.shared.b16 [%0+%5], {%1, %2, %3, %4};" ::"r"(addr), "r"(r0), "r"(r1), "r"(r2), "r"(r3), "n"(OFF) : "memory");
}
template <int OFF> __device__ __forceinline__ void stsm2(uint32_t addr, uint32_t r0, uint32_t r1) {
  asm volatile("stmatrix.sync.aligned.m8n8.x2.shared.b16 [%0+%3], {%1, %2};" ::"r"(addr), "r"(r0), "r"(r1), "n"(OFF) : "memory");
}
template <int OFF> __device__ __forceinline__ void ldsm4(uint32_t addr, uint32_t& r0, uint32_t& r1, uint32_t& r2, uint32_t& r3) {
  asm volatile("ldmatrix.sync.aligned.m8n8.x4.shared.b16 {%0, %1, %2, %3}, [%4+%5];" : "=r"(r0), "=r"(r1), "=r"(r2), "=r"(r3) : "r"(addr), "n"(OFF) : "memory");
}
template <int I, int N, class F> __device__ __forceinline__ void static_for(F&& f) {
  if constexpr (I < N) { f(std::integral_constant<int, I>{}); static_for<I + 1, N>(f); }
}
template <int N> __device__ __forceinline__ void zero_regs(float (&r)[N]) {
#pragma unroll
  for (int i = 0; i < N; i++) r[i] = 0.f;
}
template <int N> __device__ __forceinline__ void fence_regs(float (&r)[N]) {
#pragma unroll
  for (int i = 0; i < N; i++) asm volatile("" : "+f"(r[i])::"memory");
}
template <int N> __device__ __forceinline__ void fence_regs(uint32_t (&r)[N]) {
#pragma unroll
  for (int i = 0; i < N; i++) asm volatile("" : "+r"(r[i])::"memory");
}
constexpr uint32_t DESC_HI = (1024 >> 4) | (1u << 30);
__device__ __forceinline__ uint64_t mk64(uint32_t lo) { return ((uint64_t)DESC_HI << 32) | lo; }
__device__ __forceinline__ uint32_t desc_lo(uint32_t saddr, uint32_t lbo) { return ((saddr & 0x3FFFFu) >> 4) + ((lbo >> 4) << 16); }


constexpr int REG_C = 232, REG_P = 40;
constexpr int K1_GO = 1;
constexpr int PASS_KS = 13;
constexpr int PASS_KC = 13;
constexpr int RSL = 5;
constexpr int TILE = 16384;
constexpr int OFF_A = 0;
constexpr int OFF_H = 32768;
constexpr int OFF_RA = OFF_H + 34816;
constexpr int OFF_RB = OFF_RA + RSL * TILE;
constexpr int OFF_BAR = OFF_RB + RSL * TILE;
constexpr int G_SMEM = OFF_BAR + 256;
constexpr int BAR_IN0 = OFF_BAR + 32 * RSL, BAR_IN1 = BAR_IN0 + 8, BAR_HALO = BAR_IN0 + 16  , BAR_GO = BAR_IN0 + 48, BAR_DONE = BAR_IN0 + 56;
constexpr int NB_TA = 1, NB_TB = 2, NB_HE = 3, NB_A = 5, NB_G = 6, NB_C = 7, NB_WG = 8  , NB_HF = 10;

struct Ring {
  uint32_t base, full, empty;
  int slot, rel;
  uint32_t phase;
  __device__ __forceinline__ void init(uint32_t sb, int which) {
    base = sb + (which ? OFF_RB : OFF_RA);
    full = sb + OFF_BAR + which * 16 * RSL;
    empty = full + 8 * RSL;
    slot = 0; rel = 0; phase = 0;
  }
  __device__ __forceinline__ void advance() { if (++slot == RSL) { slot = 0; phase ^= 1; } }
  __device__ __forceinline__ uint32_t acquire() {
    mbar_wait_wd(full + 8 * slot, phase);
    const uint32_t a = base + slot * TILE; advance(); return a;
  }
  __device__ __forceinline__ void release(int lane, bool on = true) {
    if (on) { if (lane == 0) mbar_arrive(empty + 8 * rel); if (++rel == RSL) rel = 0; }
  }
  __device__ __forceinline__ void load(const CUtensorMap* tm, int row, int blk) {
    mbar_wait(empty + 8 * slot, phase ^ 1);
    mbar_expect_tx(full + 8 * slot, TILE);
    tma_load_3d(base + slot * TILE, tm, full + 8 * slot, 0, row, blk);
    advance();
  }
  __device__ __forceinline__ void load_n128(const CUtensorMap* tm, int nblk) {
#pragma unroll 1
    for (int kt = 0; kt < 4; kt++) load(tm, 64 * kt, 2 * nblk);
  }
  __device__ __forceinline__ void load_glu(const CUtensorMap* tm, int grp) {
#pragma unroll 1
    for (int kt = 0; kt < 4; kt++) {
      mbar_wait(empty + 8 * slot, phase ^ 1);
      mbar_expect_tx(full + 8 * slot, TILE);
      tma_load_4d(base + slot * TILE, tm, full + 8 * slot, 0, 64 * kt, 0, grp);
      advance();
    }
  }
  __device__ __forceinline__ void load_n256(const CUtensorMap* tm, int row0, int ntiles) {
#pragma unroll 1
    for (int kt = 0; kt < ntiles; kt++) load(tm, row0 + 32 * kt, 0);
  }
};

struct Frag {
  uint32_t f[4];
  __device__ __forceinline__ Frag(uint32_t base, int row, int lane, int pitch = 128) {
    const uint32_t a = base + row * pitch + ((((lane >> 4) ^ row) & 7) << 4);
#pragma unroll
    for (int j = 0; j < 4; j++) f[j] = a ^ (j << 5);
  }
};
__device__ __forceinline__ int frag_row(int warp4, int lane) { return warp4 * 16 + (lane & 15); }
template <int OFF, int NKS, int BLK = 8192> __device__ __forceinline__ void store_frags(const Frag& fr, const uint32_t (&a)[4 * NKS]) {
  static_for<0, NKS>([&](auto K) { constexpr int ks = K.value;
    stsm4<OFF + (ks >> 2) * BLK>(fr.f[ks & 3], a[4 * ks], a[4 * ks + 1], a[4 * ks + 2], a[4 * ks + 3]); });
}
template <int OFF> __device__ __forceinline__ void load_frags(const Frag& fr, uint32_t (&a)[64]) {
  static_for<0, 16>([&](auto K) { constexpr int ks = K.value;
    ldsm4<OFF + (ks >> 2) * 8192>(fr.f[ks & 3], a[4 * ks], a[4 * ks + 1], a[4 * ks + 2], a[4 * ks + 3]); });
}
__device__ __forceinline__ void unpack_acc(float (&acc)[128], const uint32_t (&a)[64], float s) {
#pragma unroll
  for (int i = 0; i < 64; i++) { acc[2 * i] = bf_lo(a[i]) * s; acc[2 * i + 1] = bf_hi(a[i]) * s; }
}
template <int N> __device__ __forceinline__ void pack_acc(const float (&acc)[2 * N], uint32_t (&a)[N]) {
#pragma unroll
  for (int i = 0; i < N; i++) a[i] = pack_bf16(acc[2 * i], acc[2 * i + 1]);
}
template <int OFF, int NKS> __device__ __forceinline__ void pack_store(const float (&acc)[8 * NKS], const Frag& fr, uint32_t off) {
  static_for<0, NKS>([&](auto K) { constexpr int ks = K.value;
    stsm4<OFF + (ks >> 2) * 8192>(fr.f[ks & 3] + off, pack_bf16(acc[8 * ks], acc[8 * ks + 1]), pack_bf16(acc[8 * ks + 2], acc[8 * ks + 3]),
          pack_bf16(acc[8 * ks + 4], acc[8 * ks + 5]), pack_bf16(acc[8 * ks + 6], acc[8 * ks + 7])); });
}
__device__ __forceinline__ void ln_stats(const float (&acc)[128], float eps, float& r0, float& c0, float& r1, float& c1) {
  float s0 = 0.f, s1 = 0.f, q0 = 0.f, q1 = 0.f, s2 = 0.f, s3 = 0.f, q2 = 0.f, q3 = 0.f;
#pragma unroll
  for (int i = 0; i < 32; i++) {
    s0 += acc[4 * i]; q0 = fmaf(acc[4 * i], acc[4 * i], q0);
    s2 += acc[4 * i + 1]; q2 = fmaf(acc[4 * i + 1], acc[4 * i + 1], q2);
    s1 += acc[4 * i + 2]; q1 = fmaf(acc[4 * i + 2], acc[4 * i + 2], q1);
    s3 += acc[4 * i + 3]; q3 = fmaf(acc[4 * i + 3], acc[4 * i + 3], q3);
  }
  s0 += s2; s1 += s3; q0 += q2; q1 += q3;
#pragma unroll
  for (int o = 1; o <= 2; o <<= 1) {
    s0 += __shfl_xor_sync(0xffffffffu, s0, o); s1 += __shfl_xor_sync(0xffffffffu, s1, o);
    q0 += __shfl_xor_sync(0xffffffffu, q0, o); q1 += __shfl_xor_sync(0xffffffffu, q1, o);
  }
  const float m0 = s0 * (1.f / 256.f), m1 = s1 * (1.f / 256.f);
  r0 = rsqrt_f(fmaxf(fmaf(q0, 1.f / 256.f, -m0 * m0), 0.f) + eps);
  r1 = rsqrt_f(fmaxf(fmaf(q1, 1.f / 256.f, -m1 * m1), 0.f) + eps);
  c0 = -m0 * r0; c1 = -m1 * r1;
}
__device__ __forceinline__ void ln_apply(const float (&acc)[128], uint32_t (&y)[64], float r0, float c0, float r1, float c1) {
#pragma unroll
  for (int i = 0; i < 32; i++) {
    y[2 * i] = pack_bf16(fmaf(acc[4 * i], r0, c0), fmaf(acc[4 * i + 1], r0, c0));
    y[2 * i + 1] = pack_bf16(fmaf(acc[4 * i + 2], r1, c1), fmaf(acc[4 * i + 3], r1, c1));
  }
}
__device__ __forceinline__ void ln_store(const float (&acc)[128], const Frag& fr, float r0, float c0, float r1, float c1) {
  static_for<0, 16>([&](auto K) { constexpr int ks = K.value;
    stsm4<OFF_A + (ks >> 2) * 8192>(fr.f[ks & 3], pack_bf16(fmaf(acc[8 * ks], r0, c0), fmaf(acc[8 * ks + 1], r0, c0)),
                                    pack_bf16(fmaf(acc[8 * ks + 2], r1, c1), fmaf(acc[8 * ks + 3], r1, c1)),
                                    pack_bf16(fmaf(acc[8 * ks + 4], r0, c0), fmaf(acc[8 * ks + 5], r0, c0)),
                                    pack_bf16(fmaf(acc[8 * ks + 6], r1, c1), fmaf(acc[8 * ks + 7], r1, c1))); });
}
template <class F>
__device__ __forceinline__ void gemm_n128_rs(float (&acc)[64], const uint32_t (&a)[64], Ring& r, int lane, int wait, int pass, F&& under_tail) {
#pragma unroll
  for (int kt = 0; kt < 4; kt++) {
    const uint32_t lo = desc_lo(r.acquire(), 8192);
    if (kt == 0 && wait > 0) nbar_sync(wait, 256);
    wg_fence();
#pragma unroll
    for (int j = 0; j < 4; j++) {
      const int ks = 4 * kt + j;
      wgmma_rs_n128<1>(acc, a[4 * ks], a[4 * ks + 1], a[4 * ks + 2], a[4 * ks + 3], mk64(lo + 128 * j), ks);
      if (ks == PASS_KS) nbar_arrive_if(pass, 256, pass > 0);
    }
    wg_commit();
    if (kt == 3) under_tail();
    if (kt > 0) { wg_wait<1>(); r.release(lane); }
  }
  wg_wait<0>(); r.release(lane);
  fence_regs(acc);
}
template <bool ACC>
__device__ __forceinline__ void gemm_n128_ss(float (&acc)[64], uint32_t alo, Ring& r, int lane, int wait, int pass) {
#pragma unroll 1
  for (int kt = 0; kt < 4; kt++) {
    const uint32_t lo = desc_lo(r.acquire(), 8192);
    if (kt == 0 && wait > 0) nbar_sync(wait, 256);
    wg_fence();
#pragma unroll
    for (int j = 0; j < 4; j++) {
      wgmma_ss_n128<1>(acc, mk64(alo + 512 * kt + 2 * j), mk64(lo + 128 * j), (ACC || j) ? 1 : kt);
      if (!ACC && j == (PASS_KS & 3)) nbar_arrive_if(pass, 256, kt == 3 && pass > 0);
    }
    wg_commit();
    wg_wait<1>();
    r.release(lane, kt > 0);
  }
  wg_wait<0>(); r.release(lane);
  fence_regs(acc);
}
__device__ __forceinline__ void ff_second(float (&acc)[128], uint32_t hlo, Ring& r, int lane) {
#pragma unroll 1
  for (int kt = 0; kt < 32; kt++) {
    const uint32_t lo = desc_lo(r.acquire(), 4096);
    const uint32_t al = hlo + 512 * ((kt >> 1) & 3) + 4 * (kt & 1);
    if (!(kt & 3)) nbar_sync(NB_HF + ((kt >> 2) & 1), 256);
    wg_fence();
    wgmma_ss_n256<1>(acc, mk64(al), mk64(lo), 1);
    wgmma_ss_n256<1>(acc, mk64(al + 2), mk64(lo + 128), 1);
    wg_commit();
    wg_wait<1>();
    r.release(lane, kt & 3);
    if ((kt & 3) == 3) {
      wg_wait<0>(); r.release(lane);
      if (kt < 24) nbar_arrive(NB_HE + ((kt >> 2) & 1), 256);
    }
  }
  wg_wait<0>();
  fence_regs(acc);
}
template <int KS>
__device__ __forceinline__ void silu_piece(const float (&acc)[64], const Frag& fr, uint32_t off) {
  uint32_t p[4];
#pragma unroll
  for (int e = 0; e < 4; e++) {
    const float h0 = acc[8 * KS + 2 * e], h1 = acc[8 * KS + 2 * e + 1];
    p[e] = pack_bf16(fmaf(h0, tanh_f(h0), h0), fmaf(h1, tanh_f(h1), h1));
  }
  stsm4<OFF_H + (KS >> 2) * 8192>(fr.f[KS & 3] + off, p[0], p[1], p[2], p[3]);
}
template <int Q>
__device__ __forceinline__ void silu_half(const float (&acc)[64], const Frag& fr, uint32_t off) {
  uint32_t p[2];
#pragma unroll
  for (int e = 0; e < 2; e++) {
    const float h0 = acc[4 * Q + 2 * e], h1 = acc[4 * Q + 2 * e + 1];
    p[e] = pack_bf16(fmaf(h0, tanh_f(h0), h0), fmaf(h1, tanh_f(h1), h1));
  }
  stsm2<OFF_H + (Q >> 3) * 8192>((fr.f[(Q >> 1) & 3] ^ ((Q & 1) << 4)) + off, p[0], p[1]);
}
template <int HB>
__device__ __forceinline__ void ff_body(float (&cur)[64], const float (&prev)[64], const uint32_t (&a)[64], Ring& r, const Frag& fr, int lane) {
  static_for<0, 4>([&](auto K) { constexpr int kt = K.value;
    const uint32_t lo = desc_lo(r.acquire(), 8192);
    if (kt == 0) nbar_sync(NB_HE + HB, 256);
    wg_fence();
    static_for<0, 4>([&](auto J) { constexpr int ks = 4 * kt + J.value;
      wgmma_rs_n128<1>(cur, a[4 * ks], a[4 * ks + 1], a[4 * ks + 2], a[4 * ks + 3], mk64(lo + 128 * J.value), ks);
      if (J.value == 3) wg_commit();
      silu_half<ks>(prev, fr, HB * 16384);
    });
    if (kt > 0) { wg_wait<1>(); r.release(lane); }
  });
  fence_async_smem();
  nbar_arrive(NB_HF + HB, 256);
  wg_wait<0>(); r.release(lane);
  fence_regs(cur);
}
template <class F>
__device__ __forceinline__ void ff_first(const uint32_t (&a)[64], Ring& r, const Frag& fr, int lane, uint32_t sb, F&& after_first) {
  float h0[64], h1[64];
  gemm_n128_rs(h0, a, r, lane, 0, 0, after_first);
#pragma unroll 1
  for (int cp = 0; cp < 3; cp++) {
    ff_body<0>(h1, h0, a, r, fr, lane);
    ff_body<1>(h0, h1, a, r, fr, lane);
  }
  ff_body<0>(h1, h0, a, r, fr, lane);
  nbar_sync(NB_HE + 1, 256);
  static_for<0, 8>([&](auto K) { silu_piece<K.value>(h1, fr, 16384); });
  fence_async_smem();
  nbar_arrive(NB_HF + 1, 256);
}
__device__ __forceinline__ void gemm_chain_setup(uint32_t sb) {
  if (sb & 1023) __trap();
#pragma unroll
  for (int i = 0; i < RSL; i++) {
    mbar_init(sb + OFF_BAR + 8 * i, 1); mbar_init(sb + OFF_BAR + 8 * (RSL + i), 4);
    mbar_init(sb + OFF_BAR + 8 * (2 * RSL + i), 1); mbar_init(sb + OFF_BAR + 8 * (3 * RSL + i), 4);
  }
#pragma unroll
  for (int i = 0; i < 7; i++) mbar_init(sb + BAR_IN0 + 8 * i, 1);
  mbar_init(sb + BAR_DONE, 8);
  fence_barrier_init();
}

struct K1Maps { CUtensorMap x, w1, w2, wqkv, x2, qkv; };

__global__ void __launch_bounds__(384, 1) k1_kernel(const __nv_bfloat16* __restrict__ x, const __grid_constant__ K1Maps tm) {
  extern __shared__ __align__(1024) uint8_t smem_raw[];
  const uint32_t sb = smem_u32(smem_raw);
  const int tid = threadIdx.x, lane = tid & 31;
  const int warp = __shfl_sync(0xffffffffu, tid >> 5, 0);
  const int row0 = blockIdx.x * 64;
  const int row = (tid >> 2) & 63, sw = row & 1;
  const uint4* src = reinterpret_cast<const uint4*>(x + (size_t)(row0 + row) * 256) + (tid & 3);
  const uint4 *src0 = src + 4 * sw, *src1 = src + 4 * (sw ^ 1);
  uint4 xv[8];
#pragma unroll
  for (int i = 0; i < 8; i++)
    asm volatile("ld.global.nc.L1::no_allocate.v4.u32 {%0,%1,%2,%3}, [%4];" : "=r"(xv[i].x), "=r"(xv[i].y), "=r"(xv[i].z), "=r"(xv[i].w)
                 : "l"(((i & 1) ? src1 : src0) + 8 * (i >> 1)));
  if (tid == 256) { prefetch_tmap(&tm.w1); prefetch_tmap(&tm.x); prefetch_tmap(&tm.w2); }
  if (tid == 0) gemm_chain_setup(sb);
  __syncthreads();
  pdl_launch();
  if (warp >= 8) {
    reg_dealloc<REG_P>();
    if (warp == 8 && lane == 0) {
      Ring r; r.init(sb, 0);
#pragma unroll 1
      for (int c = 0; c < 11; c++) {
        r.load_n128(c < 8 ? &tm.w1 : &tm.wqkv, c < 8 ? c : c - 8);
        if (c == 0) { mbar_wait(sb + OFF_BAR + 8 * K1_GO, 0); mbar_arrive(sb + BAR_GO); }
      }
    } else if (warp == 9 && lane == 0) {
      Ring r; r.init(sb, 1);
      mbar_expect_tx(sb + BAR_IN0, 32768);
      tma_load_3d(sb + OFF_H, &tm.x, sb + BAR_IN0, 0, row0, 0);
      mbar_wait(sb + BAR_GO, 0);
      r.load_n256(&tm.w2, 0, 32);
#pragma unroll 1
      for (int c = 3; c < 6; c++) r.load_n128(&tm.wqkv, c);
    } else if (warp == 10 && lane == 0) {
      mbar_wait(sb + BAR_DONE, 0);
    }
  } else {
    reg_alloc<REG_C>();
    {
      float s = 0.f, q = 0.f, s2 = 0.f, q2 = 0.f;
#pragma unroll
      for (int i = 0; i < 8; i++)
#pragma unroll
        for (int e = 0; e < 4; e++) {
          const float lo = bf_lo((&xv[i].x)[e]), hi = bf_hi((&xv[i].x)[e]);
          s += lo; q = fmaf(lo, lo, q); s2 += hi; q2 = fmaf(hi, hi, q2);
        }
      s += s2; q += q2;
      s += __shfl_xor_sync(0xffffffffu, s, 1); q += __shfl_xor_sync(0xffffffffu, q, 1);
      s += __shfl_xor_sync(0xffffffffu, s, 2); q += __shfl_xor_sync(0xffffffffu, q, 2);
      const float m = s * (1.f / 256.f);
      const float rs = 0.5f * rsqrt_f(fmaxf(fmaf(q, 1.f / 256.f, -m * m), 0.f) + LN_EPS), cs = -m * rs;
      const uint32_t dst = (sb + OFF_A + row * 128 + ((((tid & 3) ^ row) & 7) << 4)) ^ (sw << 6);
#pragma unroll
      for (int i = 0; i < 8; i++) {
        uint32_t y[4];
#pragma unroll
        for (int e = 0; e < 4; e++) y[e] = pack_bf16(fmaf(bf_lo((&xv[i].x)[e]), rs, cs), fmaf(bf_hi((&xv[i].x)[e]), rs, cs));
        asm volatile("st.shared.v4.u32 [%0], {%1,%2,%3,%4};" ::"r"((dst ^ ((i & 1) << 6)) + (i >> 1) * 8192), "r"(y[0]), "r"(y[1]), "r"(y[2]), "r"(y[3]) : "memory");
      }
    }
    nbar_sync(NB_A, 256);
    const int wg = warp >> 2;
    Ring r; r.init(sb, wg);
    const Frag fr(sb, frag_row(warp & 3, lane), lane);
    uint32_t a[64];
    if (wg == 0) {
      load_frags<OFF_A>(fr, a);
      ff_first(a, r, fr, lane, sb, [] {});
      nbar_sync(NB_A, 256);
      load_frags<OFF_A>(fr, a);
    } else {
      float acc[128];
      mbar_wait_wd(sb + BAR_IN0, 0);
      load_frags<OFF_H>(fr, a);
      unpack_acc(acc, a, 2.f);
      nbar_arrive(NB_HE, 256);
      nbar_arrive(NB_HE + 1, 256);
      ff_second(acc, desc_lo(sb + OFF_H, 16), r, lane);
      float r0, c0, r1, c1;
      ln_stats(acc, 4.f * LN_EPS, r0, c0, r1, c1);
      pack_store<OFF_H, 16>(acc, fr, 0);
      ln_apply(acc, a, r0, c0, r1, c1);
      store_frags<OFF_A, 16>(fr, a);
      fence_async_smem();
      nbar_arrive(NB_A, 256);
      nbar_sync(NB_WG + 1, 128);
      if (tid == 128) { tma_store_3d(&tm.x2, sb + OFF_H, 0, row0, 0); bulk_commit(); }
    }
    float h[64];
    const bool leader = (tid & 127) == 0;
#pragma unroll 1
    for (int j = 0; j < 3; j++) {
      gemm_n128_rs(h, a, r, lane, wg ? (j ? NB_TB : 0) : NB_TA, wg ? NB_TA : (j < 2 ? NB_TB : 0), [] {});
      if (j != 1) {
        if (leader) { if (j == 0) bulk_wait_read<0>(); else bulk_wait_read<1>(); }
        nbar_sync(NB_WG + wg, 128);
      }
      const uint32_t stage = (wg ? OFF_H : OFF_A) + (j & 1) * 16384;
      if (wg == 0 && j < 2) {
#pragma unroll
        for (int i = 0; i < 64; i++) h[i] *= Q_SCALE;
      }
      pack_store<0, 8>(h, fr, stage);
      fence_async_smem();
      nbar_sync(NB_WG + wg, 128);
      if (leader) { tma_store_3d(&tm.qkv, sb + stage, 0, row0, 2 * (3 * wg + j)); bulk_commit(); }
    }
    if (leader) bulk_wait_read<0>();
    if (lane == 0) mbar_arrive(sb + BAR_DONE);
  }
}

struct K3Maps { CUtensorMap att, x2, wo, wpw1, wpw2, w1, w2, out; };

__device__ __forceinline__ void glu(const float (&g)[64], uint32_t (&p)[16]) {
#pragma unroll
  for (int i = 0; i < 16; i++)
    p[i] = pack_bf16(fmaf(g[2 * i], tanh_f(g[32 + 2 * i]), g[2 * i]), fmaf(g[2 * i + 1], tanh_f(g[33 + 2 * i]), g[2 * i + 1]));
}
__device__ __forceinline__ void glu_store(const uint32_t (&p)[16], uint32_t sb, int grp, int warp4, int lane, uint32_t rank) {
  const int g = lane >> 2;
  if (rank == 0 ? (warp4 == 3 && g >= 6) : (warp4 == 0 && g < 2)) {
    const int R = rank == 0 ? g - 6 : 66 + g;
    uint32_t dst, bar;
    asm("mapa.shared::cluster.u32 %0, %1, %2;" : "=r"(dst) : "r"(sb + OFF_H + R * 512 + grp * 128 + 4 * (lane & 3)), "r"(rank ^ 1));
    asm("mapa.shared::cluster.u32 %0, %1, %2;" : "=r"(bar) : "r"(sb + BAR_HALO + 8 * grp), "r"(rank ^ 1));
#pragma unroll
    for (int i = 0; i < 8; i++) {
      const uint32_t v = rank == 0 ? p[2 * i + 1] : p[2 * i];
      asm volatile("st.async.shared::cluster.mbarrier::complete_tx::bytes.b32 [%0], %1, [%2];"
                   ::"r"(dst + (((i ^ R) & 7) << 4)), "r"(v), "r"(bar) : "memory");
    }
  }
  store_frags<OFF_H, 4>(Frag(sb + grp * 128, frag_row(warp4, lane) + 2, lane, 512), p);
}
__device__ __forceinline__ void conv_load(uint32_t sb, int c, int gr, uint4& v) {
  asm volatile("ld.shared.v4.u32 {%0,%1,%2,%3}, [%4];" : "=r"(v.x), "=r"(v.y), "=r"(v.z), "=r"(v.w)
               : "r"(sb + OFF_H + gr * 512 + (c >> 3) * 128 + (((c ^ gr) & 7) << 4)) : "memory");
}
template <int R> __device__ __forceinline__ void conv_row(const uint4 (&in)[8], const uint4 (&w)[5], uint4& o) {
#pragma unroll
  for (int e = 0; e < 4; e++) {
    uint32_t v = hmul2_bf16((&in[R].x)[e], (&w[0].x)[e]);
#pragma unroll
    for (int k = 1; k < 5; k++) v = hfma2_bf16((&in[R + k].x)[e], (&w[k].x)[e], v);
    const float h0 = bf_lo(v), h1 = bf_hi(v);
    (&o.x)[e] = pack_bf16(fmaf(h0, tanh_f(h0), h0), fmaf(h1, tanh_f(h1), h1));
  }
}
__device__ __forceinline__ void conv_silu(uint32_t sb, int c, int r0, const uint4 (&w)[5], uint4 (&o)[4]) {
  uint4 in[8];
#pragma unroll
  for (int i = 0; i < 8; i++) conv_load(sb, c, r0 + i, in[i]);
  static_for<0, 4>([&](auto R) { conv_row<R.value>(in, w, o[R.value]); });
}
__device__ __forceinline__ void gemm_n128_conv(float (&acc)[64], uint32_t alo, Ring& r, int lane, int wait, int pass,
                                               uint32_t sb, int c, int r0, const uint4 (&w)[5], uint4 (&o)[4]) {
  uint4 in[8];
#pragma unroll
  for (int i = 0; i < 4; i++) conv_load(sb, c, r0 + i, in[i]);
  static_for<0, 4>([&](auto K) { constexpr int kt = K.value;
    const uint32_t lo = desc_lo(r.acquire(), 8192);
    if (kt == 0 && wait > 0) nbar_sync(wait, 256);
    wg_fence();
#pragma unroll
    for (int j = 0; j < 4; j++) {
      wgmma_ss_n128<1>(acc, mk64(alo + 512 * kt + 2 * j), mk64(lo + 128 * j), kt + j);
      if (j == 0) conv_load(sb, c, r0 + 4 + kt, in[4 + kt]);
      if (4 * kt + j == PASS_KC) nbar_arrive_if(pass, 256, pass > 0);
    }
    wg_commit();
    conv_row<kt>(in, w, o[kt]);
    if (kt > 0) { wg_wait<1>(); r.release(lane); }
  });
  wg_wait<0>(); r.release(lane);
  fence_regs(acc);
}
template <int NR> __device__ __forceinline__ void conv_store(uint32_t sb, int c, int r0, const uint4 (&o)[NR]) {
#pragma unroll
  for (int r = 0; r < NR; r++)
    asm volatile("st.shared.v4.u32 [%0], {%1,%2,%3,%4};" ::"r"(sb + OFF_A + (c >> 3) * 8192 + (r0 + r) * 128 + (((c ^ (r0 + r)) & 7) << 4)),
                 "r"(o[r].x), "r"(o[r].y), "r"(o[r].z), "r"(o[r].w) : "memory");
}
__device__ __forceinline__ void load_taps(const __nv_bfloat16* dw, int c, uint4 (&w)[5]) {
#pragma unroll
  for (int k = 0; k < 5; k++)
    asm volatile("ld.global.nc.v4.u32 {%0,%1,%2,%3}, [%4];" : "=r"(w[k].x), "=r"(w[k].y), "=r"(w[k].z), "=r"(w[k].w) : "l"(dw + k * 256 + 8 * c) : "memory");
}
__device__ __forceinline__ void halve_taps(uint4 (&w)[5]) {
#pragma unroll
  for (int k = 0; k < 5; k++) {
    w[k].x = hmul2_bf16(w[k].x, 0x3f003f00u); w[k].y = hmul2_bf16(w[k].y, 0x3f003f00u);
    w[k].z = hmul2_bf16(w[k].z, 0x3f003f00u); w[k].w = hmul2_bf16(w[k].w, 0x3f003f00u);
  }
}

__global__ void __cluster_dims__(2, 1, 1) __launch_bounds__(384, 1) k3_kernel(const __grid_constant__ K3Maps tm, const __nv_bfloat16* __restrict__ dw) {
  extern __shared__ __align__(1024) uint8_t smem_raw[];
  const uint32_t sb = smem_u32(smem_raw);
  const int tid = threadIdx.x, lane = tid & 31;
  const int warp = __shfl_sync(0xffffffffu, tid >> 5, 0);
  const uint32_t rank = blockIdx.x & 1;
  const int pair = blockIdx.x >> 1, b = pair >= 33 ? 1 : 0;
  const int t0 = (pair - 33 * b) * 124 - 2 + 64 * (int)rank;
  if (tid == 256) { prefetch_tmap(&tm.x2); prefetch_tmap(&tm.wo); prefetch_tmap(&tm.att); prefetch_tmap(&tm.wpw1); }
  if (tid == 0) {
    gemm_chain_setup(sb);
#pragma unroll
    for (int i = 0; i < 4; i++) mbar_expect_tx(sb + BAR_HALO + 8 * i, 256);
  }
  __syncthreads();
  asm volatile("barrier.cluster.arrive.relaxed.aligned;" ::: "memory");
  asm volatile("barrier.cluster.wait.aligned;" ::: "memory");
  if (warp >= 8) {
    reg_dealloc<REG_P>();
    if (warp == 8 && lane == 0) {
      Ring r; r.init(sb, 0);
      mbar_wait(sb + BAR_IN1, 0);
      r.load_n128(&tm.wo, 0);
      mbar_wait(sb + BAR_IN0, 0);
      r.load_glu(&tm.wpw1, 0); r.load_glu(&tm.wpw1, 2);
      r.load_n128(&tm.wpw2, 0);
#pragma unroll 1
      for (int c = 0; c < 8; c++) r.load_n128(&tm.w1, c);
    } else if (warp == 9 && lane == 0) {
      Ring r; r.init(sb, 1);
      mbar_expect_tx(sb + BAR_IN1, 32768);
      tma_load_4d(sb + OFF_H + 1024, &tm.x2, sb + BAR_IN1, 0, t0, 0, b);
      r.load(&tm.wo, 0, 2);
      pdl_wait();
      mbar_expect_tx(sb + BAR_IN0, 32768);
      tma_load_4d(sb + OFF_A, &tm.att, sb + BAR_IN0, 0, t0, 0, b);
      r.load(&tm.wo, 64, 2); r.load(&tm.wo, 128, 2); r.load(&tm.wo, 192, 2);
      mbar_wait(sb + BAR_IN0, 0);
      r.load_glu(&tm.wpw1, 1); r.load_glu(&tm.wpw1, 3);
      r.load_n128(&tm.wpw2, 1);
      r.load_n256(&tm.w2, 0, 32);
    } else if (warp == 10 && lane == 0) {
      mbar_wait(sb + BAR_DONE, 0);
    }
  } else {
    reg_alloc<REG_C>();
    const int wg = warp >> 2;
    Ring r; r.init(sb, wg);
    const Frag fr(sb, frag_row(warp & 3, lane), lane);
    const uint32_t alo = desc_lo(sb + OFF_A, 16);
    const uint32_t stats = sb + OFF_H + (rank ? 66 * 512 : 0);
    uint32_t a[64], xk[32];
    float x[64];
    mbar_wait_wd(sb + BAR_IN1, 0);
    static_for<0, 8>([&](auto K) { constexpr int ks = K.value;
      ldsm4<OFF_H + 1024 + (ks >> 2) * 8192>(fr.f[ks & 3] + wg * 16384, xk[4 * ks], xk[4 * ks + 1], xk[4 * ks + 2], xk[4 * ks + 3]); });
#pragma unroll 1
    for (int it = 0;; it++) {
      {
        const float sc = it ? 1.f : 0.5f;
#pragma unroll
        for (int i = 0; i < 32; i++) { x[2 * i] = bf_lo(xk[i]) * sc; x[2 * i + 1] = bf_hi(xk[i]) * sc; }
      }
      if (it) nbar_sync(NB_C, 256); else mbar_wait_wd(sb + BAR_IN0, 0);
      gemm_n128_ss<true>(x, alo, r, lane, 0, 0);
      {
        float s0 = 0.f, s1 = 0.f, q0 = 0.f, q1 = 0.f, s2 = 0.f, s3 = 0.f, q2 = 0.f, q3 = 0.f;
#pragma unroll
        for (int i = 0; i < 16; i++) {
          s0 += x[4 * i]; q0 = fmaf(x[4 * i], x[4 * i], q0);
          s2 += x[4 * i + 1]; q2 = fmaf(x[4 * i + 1], x[4 * i + 1], q2);
          s1 += x[4 * i + 2]; q1 = fmaf(x[4 * i + 2], x[4 * i + 2], q1);
          s3 += x[4 * i + 3]; q3 = fmaf(x[4 * i + 3], x[4 * i + 3], q3);
        }
        s0 += s2; s1 += s3; q0 += q2; q1 += q3;
#pragma unroll
        for (int o = 1; o <= 2; o <<= 1) {
          s0 += __shfl_xor_sync(0xffffffffu, s0, o); s1 += __shfl_xor_sync(0xffffffffu, s1, o);
          q0 += __shfl_xor_sync(0xffffffffu, q0, o); q1 += __shfl_xor_sync(0xffffffffu, q1, o);
        }
        if (!(lane & 3)) asm volatile("st.shared.v4.f32 [%0], {%1,%2,%3,%4};" ::"r"(stats + wg * 512 + ((warp & 3) * 8 + (lane >> 2)) * 16),
                                      "f"(s0), "f"(q0), "f"(s1), "f"(q1) : "memory");
        nbar_sync(NB_A, 256);
        float4 o;
        asm volatile("ld.shared.v4.f32 {%0,%1,%2,%3}, [%4];" : "=f"(o.x), "=f"(o.y), "=f"(o.z), "=f"(o.w)
                     : "r"(stats + (wg ^ 1) * 512 + ((warp & 3) * 8 + (lane >> 2)) * 16) : "memory");
        const float m0 = (s0 + o.x) * (1.f / 256.f), m1 = (s1 + o.z) * (1.f / 256.f);
        const float r0 = 0.5f * rsqrt_f(fmaxf(fmaf(q0 + o.y, 1.f / 256.f, -m0 * m0), 0.f) + LN_EPS);
        const float r1 = 0.5f * rsqrt_f(fmaxf(fmaf(q1 + o.w, 1.f / 256.f, -m1 * m1), 0.f) + LN_EPS);
        const float c0 = -m0 * r0, c1 = -m1 * r1;
        static_for<0, 8>([&](auto K) { constexpr int ks = K.value;
          stsm4<OFF_A + (ks >> 2) * 8192>(fr.f[ks & 3] + wg * 16384, pack_bf16(fmaf(x[8 * ks], r0, c0), fmaf(x[8 * ks + 1], r0, c0)),
                                          pack_bf16(fmaf(x[8 * ks + 2], r1, c1), fmaf(x[8 * ks + 3], r1, c1)),
                                          pack_bf16(fmaf(x[8 * ks + 4], r0, c0), fmaf(x[8 * ks + 5], r0, c0)),
                                          pack_bf16(fmaf(x[8 * ks + 6], r1, c1), fmaf(x[8 * ks + 7], r1, c1))); });
      }
      if (it) break;
      fence_async_smem();
      pack_acc<32>(x, xk);
      nbar_sync(NB_G, 256);
      const int cc = 8 * wg + (tid & 7), r0 = 4 * ((tid >> 3) & 15);
      uint4 w[5], o0[4], o1[4];
      float g[64];
      uint32_t p[16];
      zero_regs(g);
      load_taps(dw, cc, w);
      gemm_n128_ss<false>(g, alo, r, lane, wg ? NB_TB : 0, wg ? NB_TA : NB_TB);
      glu(g, p);
      glu_store(p, sb, wg, warp & 3, lane, rank);
      halve_taps(w);
      nbar_sync(NB_WG + wg, 128);
      mbar_wait_wd(sb + BAR_HALO + 8 * wg, 0);
      gemm_n128_conv(g, alo, r, lane, wg ? NB_TB : NB_TA, wg ? 0 : NB_TB, sb, cc, r0, w, o0);
      nbar_arrive(wg ? NB_G : NB_A, 256);
      load_taps(dw, 16 + cc, w);
      glu(g, p);
      glu_store(p, sb, 2 + wg, warp & 3, lane, rank);
      halve_taps(w);
      nbar_sync(NB_WG + wg, 128);
      mbar_wait_wd(sb + BAR_HALO + 8 * (2 + wg), 0);
      conv_silu(sb, 16 + cc, r0, w, o1);
      nbar_sync(wg ? NB_A : NB_G, 256);
      conv_store<4>(sb, cc, r0, o0);
      conv_store<4>(sb, 16 + cc, r0, o1);
      fence_async_smem();
    }
    if (wg == 0) {
      nbar_sync(NB_G, 256);
      load_frags<OFF_A>(fr, a);
      ff_first(a, r, fr, lane, sb, [&] {
#pragma unroll
        for (int i = 0; i < 8; i++)
          asm volatile("st.shared.v4.u32 [%0], {%1,%2,%3,%4};" ::"r"(sb + OFF_H + 16384 + 1024 + 2048 * i + 16 * tid),
                       "r"(pack_bf16(x[8 * i], x[8 * i + 1])), "r"(pack_bf16(x[8 * i + 2], x[8 * i + 3])),
                       "r"(pack_bf16(x[8 * i + 4], x[8 * i + 5])), "r"(pack_bf16(x[8 * i + 6], x[8 * i + 7])) : "memory");
        nbar_arrive(NB_C, 256);
      });
    } else {
      nbar_arrive(NB_G, 256);
      float acc[128];
      nbar_arrive(NB_HE, 256);
      nbar_sync(NB_C, 256);
#pragma unroll
      for (int i = 0; i < 8; i++) {
        uint32_t v[4];
        asm volatile("ld.shared.v4.u32 {%0,%1,%2,%3}, [%4];" : "=r"(v[0]), "=r"(v[1]), "=r"(v[2]), "=r"(v[3]) : "r"(sb + OFF_H + 16384 + 1024 + 2048 * i + 16 * (tid - 128)) : "memory");
#pragma unroll
        for (int e = 0; e < 4; e++) { acc[8 * i + 2 * e] = 2.f * bf_lo(v[e]); acc[8 * i + 2 * e + 1] = 2.f * bf_hi(v[e]); }
      }
#pragma unroll
      for (int i = 0; i < 64; i++) acc[64 + i] = 2.f * x[i];
      nbar_arrive(NB_HE + 1, 256);
      const Frag fo(sb, (frag_row(warp & 3, lane) + (rank ? 0 : 62)) & 63, lane);
      ff_second(acc, alo + (OFF_H >> 4), r, lane);
      float r0, c0, r1, c1;
      ln_stats(acc, 4.f * LN_EPS, r0, c0, r1, c1);
      const int ts = t0 + (rank ? 0 : 2);
      ln_store(acc, fo, r0, c0, r1, c1);
      fence_async_smem();
      nbar_sync(NB_WG + 1, 128);
      if (tid == 128) {
#pragma unroll
        for (int i = 0; i < 4; i++) tma_store_3d(&tm.out, sb + OFF_A + i * 8192, 64 * i, ts, b);
        bulk_commit();
        bulk_wait_read<0>();
      }
    }
    if (lane == 0) mbar_arrive(sb + BAR_DONE);
  }
}

constexpr int AT_HALF = 16384;
constexpr int AT_STAGE = 2 * AT_HALF;
constexpr int AT_NST = 5;
constexpr int AT_LAG = 2;
constexpr int AT_NSTAGES = 32;
constexpr int AT_ONES = AT_NST * AT_STAGE;
constexpr int AT_Q = AT_ONES + 2048;
constexpr int AT_TAB = AT_Q + 32768;
constexpr int AT_BARS = AT_TAB + 32768;
constexpr int AT_SMEM = AT_BARS + 256;
constexpr int SPLITV = 4;
constexpr int AT_SPLIT = SPLITV;
constexpr int TABX = 3;
constexpr uint32_t TAB_MASK = 0x30c030c0u;
__device__ __forceinline__ float exp2_tab(float x, uint32_t tab, uint32_t rep) {
  const int t = __viaddmin_s32_relu(__float_as_int(x + 384.f), -0x43810000, 252 << 15);
  uint32_t v, o;
  asm("lop3.b32 %0, %1, %2, %3, 0xEA;" : "=r"(o) : "r"(t), "n"(0x8000u - (128u >> TABX)), "r"(rep));
  asm volatile("ld.shared.u32 %0, [%1];" : "=r"(v) : "r"(o + tab));
  return __uint_as_float(v + ((uint32_t)t << 8));
}

struct AttnCtx {
  uint32_t sbase, full, empty;
  const CUtensorMap* tm;
  int kcol, vcol, row0;
  int prod_slot;
  int lane;
};
__device__ __forceinline__ uint32_t k_lo(uint32_t sbase, int st, int sub) { return (sbase >> 4) + (1u << 16) + st * (AT_STAGE >> 4) + sub * 512; }
__device__ __forceinline__ uint32_t v_lo(uint32_t sbase, int st, int sub) {
  return (sbase >> 4) + ((AT_ONES >> 4) << 16) - 65535u * (uint32_t)(((st * AT_STAGE + AT_HALF) >> 4) + sub * 512);
}
__device__ __forceinline__ void attn_produce(const AttnCtx& c, int n, int slot, uint32_t par) {
  mbar_wait(c.empty + 8 * slot, par);
  if (elect_one()) {
    mbar_expect_tx(c.full + 8 * slot, AT_STAGE);
    tma_load_2d(c.sbase + slot * AT_STAGE, c.tm, c.full + 8 * slot, c.kcol, c.row0 + 128 * n);
    tma_load_2d(c.sbase + slot * AT_STAGE + AT_HALF, c.tm, c.full + 8 * slot, c.vcol, c.row0 + 128 * n);
  }
  __syncwarp();
}
__device__ __forceinline__ void issue_qk(float (&S)[32], const uint32_t (&Q)[16], uint32_t lo) {
#pragma unroll
  for (int ks = 0; ks < 4; ks++) wgmma_rs_n64<0>(S, Q[4 * ks], Q[4 * ks + 1], Q[4 * ks + 2], Q[4 * ks + 3], mk64(lo + 2 * ks), ks);
  wg_commit();
}
template <int NKS> __device__ __forceinline__ void issue_pv(float (&O)[36], const uint32_t (&P)[16], uint32_t lo) {
#pragma unroll
  for (int ks = 0; ks < NKS; ks++) wgmma_rs_n72<1>(O, P[4 * ks], P[4 * ks + 1], P[4 * ks + 2], P[4 * ks + 3], mk64(lo - 65535u * 128u * ks), 1);
  wg_commit();
}
template <bool safe, int SUB, bool LAST, int NI>
__device__ __forceinline__ void fast_step(const AttnCtx& c, float (&S)[32], uint32_t (&P)[16], float (&O)[36], const uint32_t (&Q)[16],
                                          int n, int st, int nst, uint32_t nph, int pst, int ld_st, uint32_t ld_par,
                                          float& m0, float& m1) {
  if (safe) {
    wg_wait<0>();
    fence_regs(O);
    float x0 = m0, x1 = m1;
#pragma unroll
    for (int i = 0; i < NI; i++) {
      x0 = fmaxf(x0, fmaxf(S[4 * i], S[4 * i + 1]));
      x1 = fmaxf(x1, fmaxf(S[4 * i + 2], S[4 * i + 3]));
    }
    x0 = fmaxf(x0, __shfl_xor_sync(0xffffffffu, x0, 1)); x1 = fmaxf(x1, __shfl_xor_sync(0xffffffffu, x1, 1));
    x0 = fmaxf(x0, __shfl_xor_sync(0xffffffffu, x0, 2)); x1 = fmaxf(x1, __shfl_xor_sync(0xffffffffu, x1, 2));
    const float a0 = ex2f(m0 - x0), a1 = ex2f(m1 - x1);
    m0 = x0; m1 = x1;
#pragma unroll
    for (int i = 0; i < 9; i++) { O[4 * i] *= a0; O[4 * i + 1] *= a0; O[4 * i + 2] *= a1; O[4 * i + 3] *= a1; }
#pragma unroll
    for (int i = 0; i < 4 * NI; i++) S[i] -= (i & 2) ? x1 : x0;
  }
  const uint32_t tab = c.sbase + AT_TAB, rep = 4 * (c.lane & ((32 >> TABX) - 1));
#pragma unroll
  for (int i = 0; i < 4 * AT_SPLIT; i++) S[i] = (!safe && ((TAB_MASK >> i) & 1)) ? exp2_tab(S[i], tab, rep) : ex2f(S[i]);
  wg_wait<0>();
  fence_regs(P);
  if (SUB == 0) {
    if (n > 0 && c.lane == 0) mbar_arrive(c.empty + 8 * pst);
    if (c.prod_slot == n % 3 && n + AT_NST - AT_LAG < AT_NSTAGES) attn_produce(c, n + AT_NST - AT_LAG, ld_st, ld_par);
  }
#pragma unroll
  for (int i = 4 * AT_SPLIT; i < 4 * NI; i++) S[i] = (!safe && ((TAB_MASK >> i) & 1)) ? exp2_tab(S[i], tab, rep) : ex2f(S[i]);
#pragma unroll
  for (int i = 0; i < 2 * NI; i++) P[i] = pack_bf16(S[2 * i], S[2 * i + 1]);
  if (SUB == 1 && !LAST) mbar_wait(c.full + 8 * nst, nph);
  wg_fence();
  if (!LAST) issue_qk(S, Q, k_lo(c.sbase, SUB ? nst : st, SUB ^ 1));
  issue_pv<NI / 2>(O, P, v_lo(c.sbase, st, SUB));
  if (LAST) { wg_wait<0>(); fence_regs(O); } else { wg_wait<1>(); fence_regs(S); }
}
__global__ void __launch_bounds__(512, 1) attn_kernel(const __grid_constant__ CUtensorMap tm_kv, const __grid_constant__ CUtensorMap tm_q,
                                                      const __grid_constant__ CUtensorMap tm_o) {
  extern __shared__ __align__(1024) uint8_t smem_raw[];
  const uint32_t sbase = smem_u32(smem_raw);
  const int tid = threadIdx.x, lane = tid & 31;
  const int warp = __shfl_sync(0xffffffffu, tid >> 5, 0);
  const int bh = blockIdx.x >> 4, qb = blockIdx.x & 15, b = bh >> 2, h = bh & 3;
  const int nwg = (qb == 15) ? 3 : 4;
  const int wg = warp >> 2;
  AttnCtx c;
  c.sbase = sbase; c.full = sbase + AT_BARS; c.empty = c.full + 8 * AT_NST; c.tm = &tm_kv;
  c.kcol = 256 + 64 * h; c.vcol = 512 + 64 * h; c.row0 = b * T_LEN;
  c.prod_slot = ((warp & 3) == 1 && wg < 3) ? wg : -1; c.lane = lane;
  const uint32_t bar_q = c.full + 16 * AT_NST, bar_v = bar_q + 32;
  if (sbase & 1023) __trap();
  if (tid == 32) { prefetch_tmap(&tm_kv); prefetch_tmap(&tm_q); prefetch_tmap(&tm_o); }
  if (tid == 0) {
#pragma unroll
    for (int i = 0; i < AT_NST; i++) { mbar_init(c.full + 8 * i, 1); mbar_init(c.empty + 8 * i, 4 * nwg); }
#pragma unroll
    for (int i = 0; i < 5; i++) mbar_init(bar_q + 8 * i, 1);
    fence_barrier_init();
  }
  asm volatile("st.shared.u32 [%0], %1;" ::"r"(sbase + AT_ONES + 4 * tid), "r"(0x3f803f80u) : "memory");
  static_assert(TABX >= 1 && TABX <= 3, "table build assumes 512..2048 bins");
#pragma unroll
  for (int j = 0; j < (1 << (TABX - 1)); j++) {
    const int i = tid + 512 * j;
    const uint32_t v = __float_as_uint(ex2f((i + 0.5f) * (1.f / (256 << TABX)))) - (126u << 23) - ((uint32_t)(2 * i + 1) << (14 - TABX));
#pragma unroll
    for (int k = 0; k < (8 >> TABX); k++)
      asm volatile("st.shared.v4.u32 [%0], {%1,%1,%1,%1};" ::"r"(sbase + AT_TAB + i * (128 >> TABX) + 16 * ((k + (tid >> TABX)) & ((8 >> TABX) - 1))), "r"(v) : "memory");
  }
  fence_async_smem();
  __syncthreads();
  pdl_wait();
  pdl_launch();
  if (wg >= nwg) return;
  const Frag fr(sbase, warp * 16 + (lane & 15), lane);
  uint32_t Q[16];
  float S[32], O[36];
  uint32_t P[16];
#pragma unroll
  for (int i = 0; i < 16; i++) Q[i] = 0;
  auto pass = [&](auto SAFE) {
    constexpr bool safe = SAFE.value;
    if (warp == 0 && elect_one()) {
      mbar_expect_tx(c.full, AT_HALF);
      tma_load_2d(sbase, &tm_kv, c.full, c.kcol, c.row0);
      if (!safe)
        for (int w = 0; w < nwg; w++) {
          mbar_expect_tx(bar_q + 8 * w, 8192);
          tma_load_2d(sbase + AT_Q + 8192 * w, &tm_q, bar_q + 8 * w, 64 * h, c.row0 + 256 * qb + 64 * w);
        }
      mbar_expect_tx(bar_v, AT_HALF);
      tma_load_2d(sbase + AT_HALF, &tm_kv, bar_v, c.vcol, c.row0);
    }
    __syncwarp();
    zero_regs(O); zero_regs(S);
#pragma unroll
    for (int i = 0; i < 16; i++) P[i] = 0;
    float m0 = -INFINITY, m1 = -INFINITY;
    if (!safe) {
      mbar_wait(bar_q + 8 * wg, 0);
#pragma unroll
      for (int ks = 0; ks < 4; ks++) ldsm4<AT_Q>(fr.f[ks], Q[4 * ks], Q[4 * ks + 1], Q[4 * ks + 2], Q[4 * ks + 3]);
    }
    mbar_wait(c.full, 0);
    if (warp == 9) for (int s = 1; s < AT_NST - AT_LAG; s++) attn_produce(c, s, s, 1);
    wg_fence();
    issue_qk(S, Q, k_lo(sbase, 0, 0));
    wg_wait<0>();
    fence_regs(S);
    mbar_wait(bar_v, safe ? 1 : 0);
    int st = 0, pst = 0; uint32_t ph = 0;
    int ld_st = AT_NST - AT_LAG; uint32_t ld_par = 1;
#pragma unroll 1
    for (int n = 0; n < AT_NSTAGES - 1; n++) {
      int nst = st + 1; uint32_t nph = ph;
      if (nst == AT_NST) { nst = 0; nph ^= 1; }
      fast_step<safe, 0, false, 8>(c, S, P, O, Q, n, st, nst, nph, pst, ld_st, ld_par, m0, m1);
      fast_step<safe, 1, false, 8>(c, S, P, O, Q, n, st, nst, nph, pst, ld_st, ld_par, m0, m1);
      pst = st; st = nst; ph = nph;
      if (++ld_st == AT_NST) { ld_st = 0; ld_par ^= 1; }
    }
    fast_step<safe, 0, true, 4>(c, S, P, O, Q, AT_NSTAGES - 1, st, st, 0, pst, ld_st, ld_par, m0, m1);
    const float r0 = rcp_f(O[32]), r1 = rcp_f(O[34]);
#pragma unroll
    for (int ks = 0; ks < 4; ks++)
      stsm4<AT_Q>(fr.f[ks], pack_bf16(O[8 * ks] * r0, O[8 * ks + 1] * r0), pack_bf16(O[8 * ks + 2] * r1, O[8 * ks + 3] * r1),
                  pack_bf16(O[8 * ks + 4] * r0, O[8 * ks + 5] * r0), pack_bf16(O[8 * ks + 6] * r1, O[8 * ks + 7] * r1));
    fence_async_smem();
    nbar_sync(3 + wg, 128);
    if ((tid & 127) == 0) {
      tma_store_3d(&tm_o, sbase + AT_Q + wg * 8192, 64 * h, 256 * qb + 64 * wg, b);
      bulk_commit();
      bulk_wait_read<0>();
    }
  };
  pass(std::false_type{});
  const float LO = 8.271806125530277e-25f  , HI = 1.2676506002282294e30f  ;
  float fin = 0.f;
#pragma unroll
  for (int i = 0; i < 32; i++) fin = fmaf(O[i], 0.f, fin);
  const bool bad = !(O[32] >= LO && O[32] <= HI && O[34] >= LO && O[34] <= HI && fin == 0.f);
  if (nbar_or(1, 128 * nwg, bad)) {
    if ((tid & 127) == 0) bulk_wait<0>();
    if (tid == 0) {
      for (int i = 0; i < AT_NST; i++) {
        mbar_inval(c.full + 8 * i); mbar_inval(c.empty + 8 * i);
        mbar_init(c.full + 8 * i, 1); mbar_init(c.empty + 8 * i, 4 * nwg);
      }
      fence_barrier_init();
      fence_async_smem();
    }
    nbar_sync(2, 128 * nwg);
    pass(std::true_type{});
  }
}

typedef CUresult (*EncodeFn)(CUtensorMap*, CUtensorMapDataType, cuuint32_t, void*, const cuuint64_t*, const cuuint64_t*, const cuuint32_t*,
                             const cuuint32_t*, CUtensorMapInterleave, CUtensorMapSwizzle, CUtensorMapL2promotion, CUtensorMapFloatOOBfill);
static EncodeFn g_encode = nullptr;

static void make_map(CUtensorMap* m, const void* ptr, int rank, const cuuint64_t* dims, const cuuint64_t* strides, const cuuint32_t* box) {
  const cuuint32_t es[4] = {1, 1, 1, 1};
  CUresult r = g_encode(m, CU_TENSOR_MAP_DATA_TYPE_BFLOAT16, rank, const_cast<void*>(ptr), dims, strides, box, es, CU_TENSOR_MAP_INTERLEAVE_NONE,
                        CU_TENSOR_MAP_SWIZZLE_128B, CU_TENSOR_MAP_L2_PROMOTION_L2_256B, CU_TENSOR_MAP_FLOAT_OOB_FILL_NONE);
  if (r != CUDA_SUCCESS) { fprintf(stderr, "cuTensorMapEncodeTiled failed (%d)\n", (int)r); abort(); }
}
static void map_blocked(CUtensorMap* m, const void* ptr, int rows, int cols, int brows, int bblk) {
  const cuuint64_t dims[3] = {64, (cuuint64_t)rows, (cuuint64_t)(cols / 64)};
  const cuuint64_t strides[2] = {(cuuint64_t)cols * 2, 128};
  const cuuint32_t box[3] = {64, (cuuint32_t)brows, (cuuint32_t)bblk};
  make_map(m, ptr, 3, dims, strides, box);
}
static void map_batched(CUtensorMap* m, const void* ptr) {
  const cuuint64_t dims[4] = {64, T_LEN, 4, 2};
  const cuuint64_t strides[3] = {512, 128, (cuuint64_t)T_LEN * 512};
  const cuuint32_t box[4] = {64, 64, 4, 1};
  make_map(m, ptr, 4, dims, strides, box);
}

extern "C" void kernel_launch(void* const* d_in, const int* in_sizes, int n_in, void* d_out, int out_size) {
  (void)in_sizes; (void)n_in; (void)out_size;
  if (!g_encode) {
    void* fn = nullptr; cudaDriverEntryPointQueryResult qr;
    cudaGetDriverEntryPoint("cuTensorMapEncodeTiled", &fn, cudaEnableDefault, &qr);
    g_encode = (EncodeFn)fn;
    cudaFuncSetAttribute(k1_kernel, cudaFuncAttributeMaxDynamicSharedMemorySize, G_SMEM);
    cudaFuncSetAttribute(attn_kernel, cudaFuncAttributeMaxDynamicSharedMemorySize, AT_SMEM);
    cudaFuncSetAttribute(k3_kernel, cudaFuncAttributeMaxDynamicSharedMemorySize, G_SMEM);
  }
  void *p_x2, *p_qkv, *p_att;
  cudaGetSymbolAddress(&p_x2, g_x2); cudaGetSymbolAddress(&p_qkv, g_qkv); cudaGetSymbolAddress(&p_att, g_att);

  K1Maps m1;
  map_blocked(&m1.x, d_in[0], M_TOT, 256, 64, 4);
  map_blocked(&m1.w1, d_in[1], 256, 1024, 64, 2);
  map_blocked(&m1.w2, d_in[2], 1024, 256, 32, 4);
  map_blocked(&m1.wqkv, d_in[3], 256, 768, 64, 2);
  map_blocked(&m1.x2, p_x2, M_TOT, 256, 64, 4);
  map_blocked(&m1.qkv, p_qkv, M_TOT, 768, 64, 2);
  CUtensorMap mkv;
  {
    const cuuint64_t dims[2] = {768, M_TOT}; const cuuint64_t strides[1] = {1536}; const cuuint32_t box[2] = {64, 128};
    make_map(&mkv, p_qkv, 2, dims, strides, box);
  }
  CUtensorMap mq;
  {
    const cuuint64_t dims[2] = {768, M_TOT}; const cuuint64_t strides[1] = {1536}; const cuuint32_t box[2] = {64, 64};
    make_map(&mq, p_qkv, 2, dims, strides, box);
  }
  CUtensorMap mo;
  {
    const cuuint64_t dims[3] = {256, T_LEN, 2}; const cuuint64_t strides[2] = {512, (cuuint64_t)T_LEN * 512}; const cuuint32_t box[3] = {64, 64, 1};
    make_map(&mo, p_att, 3, dims, strides, box);
  }
  K3Maps m3;
  map_batched(&m3.att, p_att);
  map_batched(&m3.x2, p_x2);
  map_blocked(&m3.wo, d_in[4], 256, 256, 64, 2);
  {
    const cuuint64_t dims[4] = {64, 256, 2, 4}; const cuuint64_t strides[3] = {1024, 512, 128}; const cuuint32_t box[4] = {64, 64, 2, 1};
    make_map(&m3.wpw1, d_in[5], 4, dims, strides, box);
  }
  map_blocked(&m3.wpw2, d_in[7], 256, 256, 64, 2);
  map_blocked(&m3.w1, d_in[8], 256, 1024, 64, 2);
  map_blocked(&m3.w2, d_in[9], 1024, 256, 32, 4);
  {
    const cuuint64_t dims[3] = {256, T_LEN, 2}; const cuuint64_t strides[2] = {512, (cuuint64_t)T_LEN * 512}; const cuuint32_t box[3] = {64, 62, 1};
    make_map(&m3.out, d_out, 3, dims, strides, box);
  }
  cudaStream_t stream = cudaStreamPerThread;
  cudaLaunchAttribute pdl; pdl.id = cudaLaunchAttributeProgrammaticStreamSerialization; pdl.val.programmaticStreamSerializationAllowed = 1;
  cudaLaunchConfig_t cfg = {};
  cfg.stream = stream;
  cfg.gridDim = dim3(125); cfg.blockDim = dim3(384); cfg.dynamicSmemBytes = G_SMEM; cfg.attrs = nullptr; cfg.numAttrs = 0;
  cudaLaunchKernelEx(&cfg, k1_kernel, (const __nv_bfloat16*)d_in[0], m1);
  cfg.gridDim = dim3(128); cfg.blockDim = dim3(512); cfg.dynamicSmemBytes = AT_SMEM; cfg.attrs = &pdl; cfg.numAttrs = USE_PDL;
  cudaLaunchKernelEx(&cfg, attn_kernel, mkv, mq, mo);
  cfg.gridDim = dim3(132); cfg.blockDim = dim3(384); cfg.dynamicSmemBytes = G_SMEM;
  cudaLaunchKernelEx(&cfg, k3_kernel, m3, (const __nv_bfloat16*)d_in[6]);
}
```
